```python
import torch

def _softmax(x, axis=-1):
    return torch.softmax(x, dim=axis)
def _gelu(x):
    return torch.nn.functional.gelu(x, approximate="tanh")
def _silu(x):
    return torch.nn.functional.silu(x)
def _sigmoid(x):
    return torch.sigmoid(x)
def _layernorm(x, axis=-1, eps=1e-5):
    m = x.mean(dim=axis, keepdim=True)
    v = x.var(dim=axis, keepdim=True, unbiased=False)
    return (x - m) / torch.sqrt(v + eps)
def _scatter_add(tgt, idx, src, axis=0):
    return tgt.clone().index_add_(axis, idx, src)
def _segment_sum(src, seg, n):
    out = torch.zeros((n,) + src.shape[1:], dtype=src.dtype)
    return out.index_add_(0, seg, src)
def _pad(x, pw):
    flat = tuple(v for pair in reversed(pw) for v in pair)
    return torch.nn.functional.pad(x, flat)

kernel_name = 'standalone__rezero__sampling'

def setup_inputs():

    _w = (lambda a: (lambda t: t.to(torch.bfloat16) if t.is_floating_point() else t)(torch.as_tensor(a)))
    B, S, D = 1024, 32, 448
    return {
        "x": _w((lambda *s: torch.randn(*s, dtype=torch.bfloat16) * 0.05)(B, S, D)),
        "fx": _w((lambda *s: torch.randn(*s, dtype=torch.bfloat16) * 0.8)(B, S, D)),
        "alpha": _w((lambda *s: torch.randn(*s, dtype=torch.bfloat16) * 0.8)(1) * 0.1),
    }

def reference(x, fx, alpha):
    return x + alpha * fx
```

```cpp
#include <cuda_runtime.h>
#include <cuda_bf16.h>
#include <stdint.h>

namespace {

constexpr int kThreads = 256;
constexpr int kCtasPerSm = 8;
constexpr int kHoldTiles = 4;
constexpr int kHoldersPerSm = 3;
constexpr unsigned kPaceNs = 3500;
constexpr unsigned kStaggerNs = 450;
constexpr int kMaxPolls = 1024;

__device__ unsigned int g_release;

__device__ __forceinline__ uint4 ld_stream(const uint4* p) {
    uint4 v;
    asm volatile("ld.global.nc.L1::no_allocate.v4.u32 {%0,%1,%2,%3}, [%4];"
                 : "=r"(v.x), "=r"(v.y), "=r"(v.z), "=r"(v.w) : "l"(p));
    return v;
}
__device__ __forceinline__ void st_vec(uint4* p, uint4 v) {
    asm volatile("st.global.v4.u32 [%0], {%1,%2,%3,%4};"
                 :: "l"(p), "r"(v.x), "r"(v.y), "r"(v.z), "r"(v.w) : "memory");
}
__device__ __forceinline__ unsigned ld_release() {
    unsigned v;
    asm volatile("ld.relaxed.gpu.global.u32 %0, [%1];" : "=r"(v) : "l"(&g_release) : "memory");
    return v;
}
__device__ __forceinline__ unsigned now_ns() {
    unsigned t;
    asm volatile("mov.u32 %0, %%globaltimer_lo;" : "=r"(t));
    return t;
}

__device__ __forceinline__ uint32_t rezero2(uint32_t x, uint32_t f, __nv_bfloat162 a2) {
    const __nv_bfloat162 xv = *reinterpret_cast<const __nv_bfloat162*>(&x);
    const __nv_bfloat162 fv = *reinterpret_cast<const __nv_bfloat162*>(&f);
    const __nv_bfloat162 r = __hadd2_rn(xv, __hmul2_rn(a2, fv));
    return *reinterpret_cast<const uint32_t*>(&r);
}
__device__ __forceinline__ uint4 rezero8(uint4 x, uint4 f, __nv_bfloat162 a2) {
    return make_uint4(rezero2(x.x, f.x, a2), rezero2(x.y, f.y, a2), rezero2(x.z, f.z, a2), rezero2(x.w, f.w, a2));
}

__global__ void __launch_bounds__(kThreads, kCtasPerSm)
rezero_kernel(const uint4* __restrict__ x, const uint4* __restrict__ fx,
              const __nv_bfloat16* __restrict__ alpha, uint4* __restrict__ out, int nhold) {
    const int b = blockIdx.x;
    if (b >= nhold) {
        const int i = (b + (kHoldTiles - 1) * nhold) * kThreads + threadIdx.x;
        const uint4 xv = ld_stream(x + i);
        const uint4 fv = ld_stream(fx + i);
        if (b == (int)gridDim.x - 1 && threadIdx.x == 0)
            asm volatile("red.relaxed.gpu.global.add.u32 [%0], 1;" :: "l"(&g_release) : "memory");
        st_vec(out + i, rezero8(xv, fv, __bfloat162bfloat162(*alpha)));
        return;
    }

    unsigned epoch = 0;
    if (threadIdx.x == 0) epoch = ld_release();
    const __nv_bfloat162 a2 = __bfloat162bfloat162(*alpha);
    const int i0 = b * kThreads + threadIdx.x;
    const int step = nhold * kThreads;
    const unsigned t0 = now_ns() + (b & 7) * kStaggerNs;
    uint4 r[kHoldTiles];
#pragma unroll
    for (int k = 0; k < kHoldTiles; k++) {
        const unsigned due = t0 + k * kPaceNs;
#pragma unroll 1
        for (int it = 0; it < 64; it++) {
            if ((int)(now_ns() - due) >= 0) break;
            __nanosleep(200);
        }
        const uint4 xv = ld_stream(x + i0 + k * step);
        const uint4 fv = ld_stream(fx + i0 + k * step);
        r[k] = rezero8(xv, fv, a2);
    }
    if (threadIdx.x == 0) {
#pragma unroll 1
        for (int it = 0; it < kMaxPolls; it++) {
            if (ld_release() != epoch) break;
            __nanosleep(50);
        }
    }
    __syncthreads();
#pragma unroll
    for (int k = 0; k < kHoldTiles; k++) st_vec(out + i0 + k * step, r[k]);
}

__global__ void rezero_generic_kernel(const __nv_bfloat16* __restrict__ x, const __nv_bfloat16* __restrict__ fx,
                                      const __nv_bfloat16* __restrict__ alpha, __nv_bfloat16* __restrict__ out, int n) {
    const __nv_bfloat16 a = *alpha;
    for (long long i = blockIdx.x * (long long)blockDim.x + threadIdx.x; i < n; i += (long long)gridDim.x * blockDim.x)
        out[i] = __hadd_rn(x[i], __hmul_rn(a, fx[i]));
}

}

extern "C" void kernel_launch(void* const* d_in, const int* in_sizes, int n_in,
                              void* d_out, int out_size) {
    (void)in_sizes; (void)n_in;
    const __nv_bfloat16* x = (const __nv_bfloat16*)d_in[0];
    const __nv_bfloat16* fx = (const __nv_bfloat16*)d_in[1];
    const __nv_bfloat16* alpha = (const __nv_bfloat16*)d_in[2];
    __nv_bfloat16* out = (__nv_bfloat16*)d_out;
    const int n = out_size;

    static int slots_full = -1;
    if (slots_full < 0) {
        int dev = 0, sms = 0, occ = 0;
        cudaGetDevice(&dev);
        cudaDeviceGetAttribute(&sms, cudaDevAttrMultiProcessorCount, dev);
        cudaOccupancyMaxActiveBlocksPerMultiprocessor(&occ, rezero_kernel, kThreads, 0);
        slots_full = occ >= kCtasPerSm ? sms : 0;
    }

    const int tile_elems = kThreads * 8;
    const bool aligned = ((((uintptr_t)x | (uintptr_t)fx | (uintptr_t)out) & 15) == 0);
    if (n <= 0) return;
    if (!aligned || n % tile_elems != 0) {
        rezero_generic_kernel<<<1024, 256>>>(x, fx, alpha, out, n);
        return;
    }
    const int ntiles = n / tile_elems;
    int nhold = slots_full * kHoldersPerSm;
    if (ntiles < 4 * nhold * kHoldTiles) nhold = 0;
    const int grid = ntiles - (kHoldTiles - 1) * nhold;
    rezero_kernel<<<grid, kThreads>>>((const uint4*)x, (const uint4*)fx, alpha, (uint4*)out, nhold);
}
```

```cpp
#include <cuda_runtime.h>
#include <cuda_bf16.h>
#include <stdint.h>

namespace {

constexpr int kThreads = 256;
constexpr int kTileElems = kThreads * 8;
constexpr int kCtasPerSm = 8;
constexpr int kHoldTiles = 4;
constexpr unsigned kRampNs0 = 800;
constexpr unsigned kRampNs1 = 1100;
constexpr unsigned kFirstLoadNs = 1300;
constexpr unsigned kStaggerNs = 400;
constexpr unsigned kPaceNs = 3300;
constexpr int kMaxPolls = 1024;

template <int kSms, int kTiles>
struct Plan {
    static constexpr int kHold0 = 3 * kSms;
    static constexpr int kHolders = 3 * kSms;
    static constexpr int kRamp = kSms;
    static constexpr int kGrid = kTiles - (kHoldTiles - 1) * kHolders;
    static_assert(kGrid > kCtasPerSm * kSms, "the last block must be a worker outside the first wave");
};

__device__ unsigned int g_release;

__device__ __forceinline__ uint4 ld_stream(const uint4* p) {
    uint4 v;
    asm volatile("ld.global.nc.L1::no_allocate.v4.u32 {%0,%1,%2,%3}, [%4];"
                 : "=r"(v.x), "=r"(v.y), "=r"(v.z), "=r"(v.w) : "l"(p));
    return v;
}
__device__ __forceinline__ void st_vec(uint4* p, uint4 v) {
    asm volatile("st.global.v4.u32 [%0], {%1,%2,%3,%4};"
                 :: "l"(p), "r"(v.x), "r"(v.y), "r"(v.z), "r"(v.w) : "memory");
}
__device__ __forceinline__ unsigned ld_release(const unsigned* release) {
    unsigned v;
    asm volatile("ld.relaxed.gpu.global.u32 %0, [%1];" : "=r"(v) : "l"(release) : "memory");
    return v;
}
__device__ __forceinline__ unsigned now_ns() {
    unsigned t;
    asm volatile("mov.u32 %0, %%globaltimer_lo;" : "=r"(t));
    return t;
}
template <unsigned kSleepNs>
__device__ __forceinline__ void wait_until(unsigned due) {
#pragma unroll 1
    for (int it = 0; it < 64; it++) {
        if ((int)(now_ns() - due) >= 0) break;
        __nanosleep(kSleepNs);
    }
}

__device__ __forceinline__ uint32_t rezero2(uint32_t x, uint32_t f, __nv_bfloat162 a2) {
    const __nv_bfloat162 xv = *reinterpret_cast<const __nv_bfloat162*>(&x);
    const __nv_bfloat162 fv = *reinterpret_cast<const __nv_bfloat162*>(&f);
    const __nv_bfloat162 r = __hadd2_rn(xv, __hmul2_rn(a2, fv));
    return *reinterpret_cast<const uint32_t*>(&r);
}
__device__ __forceinline__ uint4 rezero8(uint4 x, uint4 f, __nv_bfloat162 a2) {
    return make_uint4(rezero2(x.x, f.x, a2), rezero2(x.y, f.y, a2), rezero2(x.z, f.z, a2), rezero2(x.w, f.w, a2));
}

__device__ __noinline__ void ramp_delay(unsigned delay_ns) { wait_until<50>(now_ns() + delay_ns); }

template <class P>
__device__ __noinline__ void holder_cta(const uint4* __restrict__ x, const uint4* __restrict__ fx,
                                        const __nv_bfloat16* __restrict__ alpha, uint4* __restrict__ out,
                                        const unsigned* release, unsigned h, int i) {
    unsigned epoch = 0;
    if (threadIdx.x == 0) epoch = ld_release(release);
    const __nv_bfloat162 a2 = __bfloat162bfloat162(*alpha);
    const unsigned t0 = now_ns() + kFirstLoadNs + (h & 7) * kStaggerNs;
    uint4 r[kHoldTiles];
#pragma unroll
    for (int k = 0; k < kHoldTiles; k++) {
        wait_until<200>(t0 + k * kPaceNs);
        const int j = k == 0 ? i : i + (P::kGrid - P::kHold0 + (k - 1) * P::kHolders) * kThreads;
        const uint4 xv = ld_stream(x + j);
        const uint4 fv = ld_stream(fx + j);
        r[k] = rezero8(xv, fv, a2);
    }
    if (threadIdx.x == 0) {
#pragma unroll 1
        for (int it = 0; it < kMaxPolls; it++) {
            if (ld_release(release) != epoch) break;
            __nanosleep(50);
        }
    }
    __syncthreads();
#pragma unroll
    for (int k = 0; k < kHoldTiles; k++)
        st_vec(out + (k == 0 ? i : i + (P::kGrid - P::kHold0 + (k - 1) * P::kHolders) * kThreads), r[k]);
}

template <class P>
__global__ void __launch_bounds__(kThreads, kCtasPerSm)
rezero_kernel(const uint4* __restrict__ x, const uint4* __restrict__ fx,
              const __nv_bfloat16* __restrict__ alpha, uint4* __restrict__ out, unsigned* release) {
    const int b = blockIdx.x;
    const unsigned h = (unsigned)(b - P::kHold0);
    const int i = b * kThreads + threadIdx.x;
    if (h < (unsigned)(P::kHolders + 2 * P::kRamp)) {
        if (h < (unsigned)P::kHolders) {
            holder_cta<P>(x, fx, alpha, out, release, h, i);
            return;
        }
        ramp_delay(h < (unsigned)(P::kHolders + P::kRamp) ? kRampNs0 : kRampNs1);
    }
    const uint4 xv = ld_stream(x + i);
    const uint4 fv = ld_stream(fx + i);
    if (b == P::kGrid - 1 && threadIdx.x == 0)
        asm volatile("red.relaxed.gpu.global.add.u32 [%0], 1;" :: "l"(release) : "memory");
    st_vec(out + i, rezero8(xv, fv, __bfloat162bfloat162(*alpha)));
}

__global__ void __launch_bounds__(kThreads)
rezero_flat_kernel(const uint4* __restrict__ x, const uint4* __restrict__ fx,
                   const __nv_bfloat16* __restrict__ alpha, uint4* __restrict__ out) {
    const size_t i = (size_t)blockIdx.x * kThreads + threadIdx.x;
    const uint4 xv = ld_stream(x + i);
    const uint4 fv = ld_stream(fx + i);
    st_vec(out + i, rezero8(xv, fv, __bfloat162bfloat162(*alpha)));
}

__global__ void rezero_generic_kernel(const __nv_bfloat16* __restrict__ x, const __nv_bfloat16* __restrict__ fx,
                                      const __nv_bfloat16* __restrict__ alpha, __nv_bfloat16* __restrict__ out, int n) {
    const __nv_bfloat16 a = *alpha;
    for (long long i = blockIdx.x * (long long)blockDim.x + threadIdx.x; i < n; i += (long long)gridDim.x * blockDim.x)
        out[i] = __hadd_rn(x[i], __hmul_rn(a, fx[i]));
}

constexpr int kPlanSms = 132;
constexpr int kPlanTiles = 1024 * 32 * 448 / kTileElems;
using MainPlan = Plan<kPlanSms, kPlanTiles>;

}

extern "C" void kernel_launch(void* const* d_in, const int* in_sizes, int n_in,
                              void* d_out, int out_size) {
    (void)in_sizes; (void)n_in;
    const __nv_bfloat16* x = (const __nv_bfloat16*)d_in[0];
    const __nv_bfloat16* fx = (const __nv_bfloat16*)d_in[1];
    const __nv_bfloat16* alpha = (const __nv_bfloat16*)d_in[2];
    __nv_bfloat16* out = (__nv_bfloat16*)d_out;
    const int n = out_size;

    static int device_matches_plan = -1;
    static unsigned* release = nullptr;
    if (device_matches_plan < 0) {
        int dev = 0, sms = 0, occ = 0;
        cudaGetSymbolAddress((void**)&release, g_release);
        cudaGetDevice(&dev);
        cudaDeviceGetAttribute(&sms, cudaDevAttrMultiProcessorCount, dev);
        cudaOccupancyMaxActiveBlocksPerMultiprocessor(&occ, rezero_kernel<MainPlan>, kThreads, 0);
        device_matches_plan = (sms == kPlanSms && occ >= kCtasPerSm && release != nullptr) ? 1 : 0;
    }

    if (n <= 0) return;
    const bool aligned = ((((uintptr_t)x | (uintptr_t)fx | (uintptr_t)out) & 15) == 0);
    if (!aligned || n % kTileElems != 0) {
        rezero_generic_kernel<<<1024, 256>>>(x, fx, alpha, out, n);
    } else if (device_matches_plan && n / kTileElems == kPlanTiles) {
        rezero_kernel<MainPlan><<<MainPlan::kGrid, kThreads>>>((const uint4*)x, (const uint4*)fx, alpha,
                                                               (uint4*)out, release);
    } else {
        rezero_flat_kernel<<<n / kTileElems, kThreads>>>((const uint4*)x, (const uint4*)fx, alpha, (uint4*)out);
    }
}
```
